```python
import torch

def _softmax(x, axis=-1):
    return torch.softmax(x, dim=axis)
def _gelu(x):
    return torch.nn.functional.gelu(x, approximate="tanh")
def _silu(x):
    return torch.nn.functional.silu(x)
def _sigmoid(x):
    return torch.sigmoid(x)
def _layernorm(x, axis=-1, eps=1e-5):
    m = x.mean(dim=axis, keepdim=True)
    v = x.var(dim=axis, keepdim=True, unbiased=False)
    return (x - m) / torch.sqrt(v + eps)
def _scatter_add(tgt, idx, src, axis=0):
    return tgt.clone().index_add_(axis, idx, src)
def _segment_sum(src, seg, n):
    out = torch.zeros((n,) + src.shape[1:], dtype=src.dtype)
    return out.index_add_(0, seg, src)
def _pad(x, pw):
    flat = tuple(v for pair in reversed(pw) for v in pair)
    return torch.nn.functional.pad(x, flat)

kernel_name = 'parallel_sum__ssm_conv_s4d__geglu_ffn__prompt'

def setup_inputs():

    _w = (lambda a: (lambda t: t.to(torch.bfloat16) if t.is_floating_point() else t)(torch.as_tensor(a)))
    def _A_setup():
        Bsz, L, D, N = 1, 2048, 512, 128
        return {
            "u": _w((lambda *s: torch.randn(*s, dtype=torch.bfloat16) * 0.05)(Bsz, L, D)),
            "log_A_real": _w((lambda *s: torch.randn(*s, dtype=torch.bfloat16) * 3.2)(D, N) * 0.5),
            "A_imag": _w((lambda *s: torch.randn(*s, dtype=torch.bfloat16) * 0.1)(D, N) * 3.14),
            "C_real": _w((lambda *s: torch.randn(*s, dtype=torch.bfloat16) * 1.6)(D, N) / N ** 0.5),
            "C_imag": _w((lambda *s: torch.randn(*s, dtype=torch.bfloat16) * 1.6)(D, N) / N ** 0.5),
            "log_dt": _w((lambda *s: torch.randn(*s, dtype=torch.bfloat16) * 0.1)(D) * 0.5 - 4.0),
            "D_skip": _w((lambda *s: torch.randn(*s, dtype=torch.bfloat16) * 0.2)(D)),
        }
    _A_in = _A_setup()

    def _B_setup():
        B, S, D, F = 1, 2048, 512, 1792
        return {
            "x": _w((lambda *s: torch.randn(*s, dtype=torch.bfloat16) * 0.05)(B, S, D)),
            "w_gate": _w((lambda *s: torch.randn(*s, dtype=torch.bfloat16) * 0.05)(D, F)),
            "w_up": _w((lambda *s: torch.randn(*s, dtype=torch.bfloat16) * 0.05)(D, F)),
            "w_down": _w((lambda *s: torch.randn(*s, dtype=torch.bfloat16) * 0.05)(F, D)),
        }
    _B_in = _B_setup()

    return {
        "A_u": _A_in["u"],
        "A_log_A_real": _A_in["log_A_real"],
        "A_A_imag": _A_in["A_imag"],
        "A_C_real": _A_in["C_real"],
        "A_C_imag": _A_in["C_imag"],
        "A_log_dt": _A_in["log_dt"],
        "A_D_skip": _A_in["D_skip"],
        "B_x": _B_in["x"],
        "B_w_gate": _B_in["w_gate"],
        "B_w_up": _B_in["w_up"],
        "B_w_down": _B_in["w_down"],
    }

def reference(A_u, A_log_A_real, A_A_imag, A_C_real, A_C_imag, A_log_dt, A_D_skip, B_x, B_w_gate, B_w_up, B_w_down):
    def _A_ref(u, log_A_real, A_imag, C_real, C_imag, log_dt, D_skip):
        L = u.shape[1]
        dt = torch.exp(log_dt)
        A = -torch.exp(log_A_real) + 1j * A_imag
        C = (C_real + 1j * C_imag) * dt[:, None]
        pos = (lambda x, dt: x.to(dt))(torch.arange(L), log_dt.dtype)
        P = torch.exp((A * dt[:, None])[:, :, None] * pos[None, None, :])
        K = 2.0 * torch.einsum("dn,dnl->dl", C, P).real
        L2 = 2 * L
        u_t = (lambda x, *d: x.permute(*d))(u, 0, 2, 1)
        Kf = (lambda x, *a, **k: torch.fft.rfft(x.float(), *a, **k))(K, L2)
        Uf = (lambda x, *a, **k: torch.fft.rfft(x.float(), *a, **k))(u_t, L2)
        y = (lambda x, *a, **k: torch.fft.irfft(x, *a, **k).to(torch.bfloat16))(Uf * Kf[None, :, :], L2)[:, :, :L]
        y = (lambda x, *d: x.permute(*d))(y, 0, 2, 1)
        return y + u * D_skip[None, None, :]

    def _B_ref(x, w_gate, w_up, w_down):
        return (_gelu(x @ w_gate) * (x @ w_up)) @ w_down

    x = A_u
    xn = _layernorm(x, axis=-1)
    return x + _A_ref(xn, A_log_A_real, A_A_imag, A_C_real, A_C_imag, A_log_dt, A_D_skip) + _B_ref(xn, B_w_gate, B_w_up, B_w_down)
```

```cpp
#include <cuda_runtime.h>
#include <cuda_bf16.h>
#include <cuda.h>
#include <stdint.h>

namespace {

typedef __nv_bfloat16 bf16;

constexpr int L_ = 2048, D_ = 512, F_ = 1792, NM_ = 128;
constexpr int NCTA = 128;
constexpr int NTHREADS = 512;

constexpr uint32_t SLOT = 16384;
constexpr uint32_t OFF_RING = 0;
constexpr uint32_t OFF_TEMP = 9 * SLOT;
constexpr uint32_t OFF_STAGE = 13 * SLOT;
constexpr uint32_t OFF_BAR = 14 * SLOT;
constexpr uint32_t SMEM_BYTES = OFF_BAR + 1024 + 1024;
constexpr uint32_t PTAB_BYTES = 8448;
constexpr uint32_t UBUF_BYTES = 6144;
constexpr uint32_t OFF_PTAB = OFF_TEMP;
constexpr uint32_t OFF_UBUF = OFF_TEMP + 4 * PTAB_BYTES;
constexpr uint32_t OFF_KDB = OFF_UBUF + 4 * UBUF_BYTES;
constexpr uint32_t CST = 24576;
constexpr int B_FULL = 0;
constexpr int B_EMPTY = 13;
constexpr int NST2 = 8;
constexpr int B_FULL2 = 26;
constexpr int B_EMPTY2 = 61;
constexpr int B_KGEN = 38;
constexpr int B_CONV = 39;
constexpr int B_UF = 40;
constexpr int B_XN = 41;
constexpr int B_H = 42;
constexpr int B_Y = 43;
constexpr int B_H2 = 45;
constexpr int B_KD = 44;
constexpr int B_HF = 70;
constexpr int B_HE = 86;

__device__ __align__(1024) bf16 g_xnT[D_ * L_];
__device__ __align__(1024) bf16 g_yT[D_ * L_];
__device__ __align__(1024) bf16 g_h[L_ * F_];
__device__ unsigned int g_cnt[64];

#define TS(i)
struct Params {
  const bf16 *lar, *aim, *cre, *cim, *logdt, *dskip;
  bf16* out;
};

__device__ __forceinline__ uint32_t smem_u32(const void* p) { return (uint32_t)__cvta_generic_to_shared(p); }
__device__ __forceinline__ void mbar_init(uint32_t bar, uint32_t cnt) {
  asm volatile("mbarrier.init.shared::cta.b64 [%0], %1;" ::"r"(bar), "r"(cnt));
}
__device__ __forceinline__ void mbar_expect_tx(uint32_t bar, uint32_t bytes) {
  asm volatile("mbarrier.arrive.expect_tx.shared::cta.b64 _, [%0], %1;" ::"r"(bar), "r"(bytes) : "memory");
}
__device__ __forceinline__ void mbar_arrive(uint32_t bar) {
  asm volatile("mbarrier.arrive.shared::cta.b64 _, [%0];" ::"r"(bar) : "memory");
}
__device__ __forceinline__ void mbar_arrive_cluster(uint32_t bar, uint32_t cta) {
  asm volatile(
      "{\n.reg .b32 ra;\nmapa.shared::cluster.u32 ra, %0, %1;\nmbarrier.arrive.shared::cluster.b64 _, [ra];\n}" ::"r"(bar),
      "r"(cta)
      : "memory");
}
__device__ __forceinline__ bool mbar_try(uint32_t bar, uint32_t parity) {
  uint32_t ok;
  asm volatile(
      "{\n.reg .pred p;\nmbarrier.try_wait.parity.shared::cta.b64 p, [%1], %2;\nselp.u32 %0, 1, 0, p;\n}"
      : "=r"(ok)
      : "r"(bar), "r"(parity)
      : "memory");
  return ok != 0;
}
__device__ __forceinline__ bool mbar_test(uint32_t bar, uint32_t parity) {
  uint32_t ok;
  asm volatile(
      "{\n.reg .pred p;\nmbarrier.test_wait.parity.shared::cta.b64 p, [%1], %2;\nselp.u32 %0, 1, 0, p;\n}"
      : "=r"(ok)
      : "r"(bar), "r"(parity)
      : "memory");
  return ok != 0;
}
#define WAIT_LIM_M (1u << 22)
#define WAIT_LIM_P (1u << 24)
__device__ __forceinline__ void mbar_wait(uint32_t bar, uint32_t parity) {
  if (mbar_try(bar, parity)) return;
  uint32_t n = 0;
  while (!mbar_try(bar, parity)) {
    if (++n > WAIT_LIM_M) __trap();
  }
}
__device__ __forceinline__ void mbar_wait_sleep(uint32_t bar, uint32_t parity) {
  uint32_t n = 0;
  while (!mbar_try(bar, parity)) {
    __nanosleep(200);
    if (++n > (1u << 22)) __trap();
  }
}
__device__ __forceinline__ void poll_ge(const unsigned int* p, unsigned int target) {
  uint32_t n = 0;
  while (true) {
    unsigned int v;
    asm volatile("ld.acquire.gpu.global.u32 %0, [%1];" : "=r"(v) : "l"(p) : "memory");
    if (v >= target) break;
    __nanosleep(32);
    if (++n > WAIT_LIM_P) __trap();
  }
}
__device__ __forceinline__ void red_release(unsigned int* p) {
  asm volatile("red.release.gpu.global.add.u32 [%0], 1;" ::"l"(p) : "memory");
}
__device__ __forceinline__ void fence_proxy_async() { asm volatile("fence.proxy.async;" ::: "memory"); }
__device__ __forceinline__ void cluster_sync_all() {
  asm volatile("barrier.cluster.arrive.relaxed.aligned;\nbarrier.cluster.wait.aligned;" ::: "memory");
}
__device__ __forceinline__ void tma_load(uint32_t dst, const CUtensorMap* tm, uint32_t bar, int c0, int c1) {
  asm volatile(
      "cp.async.bulk.tensor.2d.shared::cluster.global.mbarrier::complete_tx::bytes [%0], [%1, {%3, %4}], [%2];" ::"r"(dst),
      "l"(tm), "r"(bar), "r"(c0), "r"(c1)
      : "memory");
}
__device__ __forceinline__ void tma_load_mc(uint32_t dst, const CUtensorMap* tm, uint32_t bar, int c0, int c1) {
  asm volatile(
      "cp.async.bulk.tensor.2d.shared::cluster.global.mbarrier::complete_tx::bytes.multicast::cluster [%0], [%1, {%3, "
      "%4}], [%2], %5;" ::"r"(dst),
      "l"(tm), "r"(bar), "r"(c0), "r"(c1), "h"((uint16_t)3)
      : "memory");
}
__device__ __forceinline__ void ldsm4(uint32_t& r0, uint32_t& r1, uint32_t& r2, uint32_t& r3, uint32_t addr) {
  asm volatile("ldmatrix.sync.aligned.m8n8.x4.shared.b16 {%0,%1,%2,%3}, [%4];"
               : "=r"(r0), "=r"(r1), "=r"(r2), "=r"(r3)
               : "r"(addr)
               : "memory");
}
__device__ __forceinline__ void ldsm4t(uint32_t& r0, uint32_t& r1, uint32_t& r2, uint32_t& r3, uint32_t addr) {
  asm volatile("ldmatrix.sync.aligned.m8n8.x4.trans.shared.b16 {%0,%1,%2,%3}, [%4];"
               : "=r"(r0), "=r"(r1), "=r"(r2), "=r"(r3)
               : "r"(addr)
               : "memory");
}
__device__ __forceinline__ void stsm4(uint32_t addr, uint32_t r0, uint32_t r1, uint32_t r2, uint32_t r3) {
  asm volatile("stmatrix.sync.aligned.m8n8.x4.shared.b16 [%0], {%1,%2,%3,%4};" ::"r"(addr), "r"(r0), "r"(r1), "r"(r2),
               "r"(r3)
               : "memory");
}
__device__ __forceinline__ void stsm4t(uint32_t addr, uint32_t r0, uint32_t r1, uint32_t r2, uint32_t r3) {
  asm volatile("stmatrix.sync.aligned.m8n8.x4.trans.shared.b16 [%0], {%1,%2,%3,%4};" ::"r"(addr), "r"(r0), "r"(r1),
               "r"(r2), "r"(r3)
               : "memory");
}
__device__ __forceinline__ uint32_t lds32(uint32_t addr) {
  uint32_t v;
  asm volatile("ld.shared.b32 %0, [%1];" : "=r"(v) : "r"(addr) : "memory");
  return v;
}
__device__ __forceinline__ void sts32(uint32_t addr, uint32_t v) {
  asm volatile("st.shared.b32 [%0], %1;" ::"r"(addr), "r"(v) : "memory");
}
__device__ __forceinline__ void sts16(uint32_t addr, uint16_t v) {
  asm volatile("st.shared.b16 [%0], %1;" ::"r"(addr), "h"(v) : "memory");
}
__device__ __forceinline__ uint4 lds128(uint32_t addr) {
  uint4 v;
  asm volatile("ld.shared.v4.b32 {%0,%1,%2,%3}, [%4];" : "=r"(v.x), "=r"(v.y), "=r"(v.z), "=r"(v.w) : "r"(addr) : "memory");
  return v;
}
__device__ __forceinline__ void sts128(uint32_t addr, uint4 v) {
  asm volatile("st.shared.v4.b32 [%0], {%1,%2,%3,%4};" ::"r"(addr), "r"(v.x), "r"(v.y), "r"(v.z), "r"(v.w) : "memory");
}
__device__ __forceinline__ uint4 ldg_cg128(const void* p) {
  uint4 v;
  asm volatile("ld.global.cg.v4.b32 {%0,%1,%2,%3}, [%4];" : "=r"(v.x), "=r"(v.y), "=r"(v.z), "=r"(v.w) : "l"(p) : "memory");
  return v;
}
__device__ __forceinline__ void stg128(void* p, uint4 v) {
  asm volatile("st.global.v4.b32 [%0], {%1,%2,%3,%4};" ::"l"(p), "r"(v.x), "r"(v.y), "r"(v.z), "r"(v.w) : "memory");
}
__device__ __forceinline__ void mma16816(float* c, uint32_t a0, uint32_t a1, uint32_t a2, uint32_t a3, uint32_t b0,
                                         uint32_t b1) {
  asm volatile(
      "mma.sync.aligned.m16n8k16.row.col.f32.bf16.bf16.f32 {%0,%1,%2,%3},{%4,%5,%6,%7},{%8,%9},{%0,%1,%2,%3};"
      : "+f"(c[0]), "+f"(c[1]), "+f"(c[2]), "+f"(c[3])
      : "r"(a0), "r"(a1), "r"(a2), "r"(a3), "r"(b0), "r"(b1));
}
__device__ __forceinline__ uint32_t pack_bf16(float lo, float hi) {
  uint32_t r;
  asm("cvt.rn.bf16x2.f32 %0, %1, %2;" : "=r"(r) : "f"(hi), "f"(lo));
  return r;
}
__device__ __forceinline__ float bf_lo(uint32_t v) { return __uint_as_float(v << 16); }
__device__ __forceinline__ float bf_hi(uint32_t v) { return __uint_as_float(v & 0xffff0000u); }
__device__ __forceinline__ float bf16r(float v) { return __bfloat162float(__float2bfloat16_rn(v)); }
__device__ __forceinline__ uint32_t hsub2_bf(uint32_t a, uint32_t b) {
  uint32_t r;
  asm("sub.rn.bf16x2 %0, %1, %2;" : "=r"(r) : "r"(a), "r"(b));
  return r;
}
__device__ __forceinline__ uint32_t hadd2_bf(uint32_t a, uint32_t b) {
  uint32_t r;
  asm("add.rn.bf16x2 %0, %1, %2;" : "=r"(r) : "r"(a), "r"(b));
  return r;
}
__device__ __forceinline__ uint32_t hmul2_bf(uint32_t a, uint32_t b) {
  uint32_t r;
  asm("mul.rn.bf16x2 %0, %1, %2;" : "=r"(r) : "r"(a), "r"(b));
  return r;
}
__device__ __forceinline__ uint32_t hfma2_bf(uint32_t a, uint32_t b, uint32_t c) {
  uint32_t r;
  asm("fma.rn.bf16x2 %0, %1, %2, %3;" : "=r"(r) : "r"(a), "r"(b), "r"(c));
  return r;
}
__device__ __forceinline__ float ex2_approx(float x) {
  float r;
  asm("ex2.approx.ftz.f32 %0, %1;" : "=f"(r) : "f"(x));
  return r;
}
__device__ __forceinline__ float tanh_approx(float x) {
  float r;
  asm("tanh.approx.f32 %0, %1;" : "=f"(r) : "f"(x));
  return r;
}
__device__ __forceinline__ uint64_t mkdesc(uint32_t addr, uint32_t lbo, uint32_t sbo, uint32_t swz = 1) {
  return (uint64_t)((addr & 0x3FFFF) >> 4) | ((uint64_t)(lbo >> 4) << 16) | ((uint64_t)(sbo >> 4) << 32) |
         ((uint64_t)swz << 62);
}
__device__ __forceinline__ void wg_fence() { asm volatile("wgmma.fence.sync.aligned;" ::: "memory"); }
__device__ __forceinline__ void wg_commit() { asm volatile("wgmma.commit_group.sync.aligned;" ::: "memory"); }
template <int N>
__device__ __forceinline__ void wg_wait() {
  asm volatile("wgmma.wait_group.sync.aligned %0;" ::"n"(N) : "memory");
}
#define R8(a, o) \
  "+f"(a[o + 0]), "+f"(a[o + 1]), "+f"(a[o + 2]), "+f"(a[o + 3]), "+f"(a[o + 4]), "+f"(a[o + 5]), "+f"(a[o + 6]), "+f"(a[o + 7])
__device__ __forceinline__ void wg_rs_n64(float* d, const uint32_t* a, uint64_t db, int sc) {
  asm volatile(
      "{\n.reg .pred p;\nsetp.ne.b32 p, %37, 0;\n"
      "wgmma.mma_async.sync.aligned.m64n64k16.f32.bf16.bf16 "
      "{%0,%1,%2,%3,%4,%5,%6,%7,%8,%9,%10,%11,%12,%13,%14,%15,%16,%17,%18,%19,%20,%21,%22,%23,%24,%25,%26,%27,%28,%29,%30,%"
      "31}, {%32,%33,%34,%35}, %36, p, 1, 1, 1;\n}"
      : R8(d, 0), R8(d, 8), R8(d, 16), R8(d, 24)
      : "r"(a[0]), "r"(a[1]), "r"(a[2]), "r"(a[3]), "l"(db), "r"(sc));
}
__device__ __forceinline__ void wg_rs_n128(float* d, const uint32_t* a, uint64_t db, int sc) {
  asm volatile(
      "{\n.reg .pred p;\nsetp.ne.b32 p, %69, 0;\n"
      "wgmma.mma_async.sync.aligned.m64n128k16.f32.bf16.bf16 "
      "{%0,%1,%2,%3,%4,%5,%6,%7,%8,%9,%10,%11,%12,%13,%14,%15,%16,%17,%18,%19,%20,%21,%22,%23,%24,%25,%26,%27,%28,%29,%30,%"
      "31,%32,%33,%34,%35,%36,%37,%38,%39,%40,%41,%42,%43,%44,%45,%46,%47,%48,%49,%50,%51,%52,%53,%54,%55,%56,%57,%58,%59,%"
      "60,%61,%62,%63}, {%64,%65,%66,%67}, %68, p, 1, 1, 1;\n}"
      : R8(d, 0), R8(d, 8), R8(d, 16), R8(d, 24), R8(d, 32), R8(d, 40), R8(d, 48), R8(d, 56)
      : "r"(a[0]), "r"(a[1]), "r"(a[2]), "r"(a[3]), "l"(db), "r"(sc));
}
__device__ __forceinline__ void wg_ss_n64(float* d, uint64_t da, uint64_t db, int sc) {
  asm volatile(
      "{\n.reg .pred p;\nsetp.ne.b32 p, %34, 0;\n"
      "wgmma.mma_async.sync.aligned.m64n64k16.f32.bf16.bf16 "
      "{%0,%1,%2,%3,%4,%5,%6,%7,%8,%9,%10,%11,%12,%13,%14,%15,%16,%17,%18,%19,%20,%21,%22,%23,%24,%25,%26,%27,%28,%29,%30,%"
      "31}, %32, %33, p, 1, 1, 0, 1;\n}"
      : R8(d, 0), R8(d, 8), R8(d, 16), R8(d, 24)
      : "l"(da), "l"(db), "r"(sc));
}
__device__ __forceinline__ void named_bar_sync(int id, int n) {
  asm volatile("bar.sync %0, %1;" ::"r"(id), "r"(n) : "memory");
}

__device__ __forceinline__ float gelu_tanh(float g) {
  float z = g * (0.7978845608028654f + 0.035677408136300125f * g * g);
  float t = tanh_approx(z);
  return g * (0.5f + 0.5f * t);
}

__device__ __forceinline__ void cexp_pos(float rl2, float tr, float x, float& er, float& ei) {
  float mag = ex2_approx(rl2 * x);
  float ph = tr * x;
  ph -= rintf(ph);
  float ang = ph * 6.283185307179586f;
  er = mag * __cosf(ang);
  ei = mag * __sinf(ang);
}
__device__ __forceinline__ int kidx(int x) {
  const int e = max(0, 24 - __clz(x));
  const int add = ((1 << e) >> 1) - 1 + ((x >> e) & 1);
  return 128 * e + ((x + (e ? add : 0)) >> e);
}
__device__ __forceinline__ float2 csq(float2 a) { return make_float2(a.x * a.x - a.y * a.y, 2.f * a.x * a.y); }
__device__ __forceinline__ float2 cmul(float2 a, float2 b) {
  return make_float2(a.x * b.x - a.y * b.y, a.x * b.y + a.y * b.x);
}
__device__ __forceinline__ uint32_t to_tf32(float v) { return __float_as_uint(v) + 0x1000u; }
__device__ __forceinline__ void mma_tf32(float* c, float a0, float a1, float a2, float a3, float b0, float b1) {
  asm volatile(
      "mma.sync.aligned.m16n8k8.row.col.f32.tf32.tf32.f32 {%0,%1,%2,%3},{%4,%5,%6,%7},{%8,%9},{%0,%1,%2,%3};"
      : "+f"(c[0]), "+f"(c[1]), "+f"(c[2]), "+f"(c[3])
      : "r"(__float_as_uint(a0)), "r"(__float_as_uint(a1)), "r"(__float_as_uint(a2)), "r"(__float_as_uint(a3)),
        "r"(__float_as_uint(b0)), "r"(__float_as_uint(b1)));
}
__device__ __forceinline__ void split_pack(float a, float b, uint32_t& hi, uint32_t& lo) {
  hi = pack_bf16(a, b);
  lo = pack_bf16(a - bf_lo(hi), b - bf_hi(hi));
}

__device__ __forceinline__ void unit_epilogue(const uint32_t* gp, const uint32_t* up, uint32_t stg,
                                              bf16* hptr  , int lane) {
  uint32_t hp[8];
#pragma unroll
  for (int j = 0; j < 8; j++) {
    uint32_t ge = pack_bf16(gelu_tanh(bf_lo(gp[j])), gelu_tanh(bf_hi(gp[j])));
    hp[j] = hmul2_bf(ge, up[j]);
  }
  const int jm = lane >> 3, rho = lane & 7;
  const int row = (jm & 1) * 8 + rho;
#pragma unroll
  for (int j = 0; j < 4; j += 2)
    stsm4(stg + row * 80 + ((j + (jm >> 1)) << 4), hp[2 * j], hp[2 * j + 1], hp[2 * j + 2], hp[2 * j + 3]);
  __syncwarp();
#pragma unroll
  for (int it = 0; it < 2; it++) {
    int r = it * 8 + (lane >> 2), c = lane & 3;
    uint4 v = lds128(stg + r * 80 + (c << 4));
    stg128(hptr + (size_t)r * F_ + c * 8, v);
  }
  __syncwarp();
}

struct KConst {
  float rl2, tr;
  float2 V1, V2, V4, V8, C, C4, C8, C16;
};
__device__ __forceinline__ void kconst(KConst& k, float& k2048, uint32_t w0, uint32_t w1, float dt, bool valid) {
  const float ar = -bf16r(expf(bf_lo(w0)));
  k.rl2 = (ar * dt) * 1.4426950408889634f;
  k.tr = (bf_hi(w0) * dt) * 0.15915494309189535f;
  k.C = make_float2(2.f * (bf_lo(w1) * dt), 2.f * (bf_hi(w1) * dt));
  float2 V16, V32;
  cexp_pos(k.rl2, k.tr, 64.f, k.V1.x, k.V1.y);
  cexp_pos(k.rl2, k.tr, 128.f, k.V2.x, k.V2.y);
  cexp_pos(k.rl2, k.tr, 256.f, k.V4.x, k.V4.y);
  cexp_pos(k.rl2, k.tr, 512.f, k.V8.x, k.V8.y);
  cexp_pos(k.rl2, k.tr, 1024.f, V16.x, V16.y);
  cexp_pos(k.rl2, k.tr, 2048.f, V32.x, V32.y);
  k.C4 = cmul(k.C, k.V4);
  k.C8 = cmul(k.C, k.V8);
  k.C16 = cmul(k.C, V16);
  if (valid) k2048 += k.C.x * V32.x - k.C.y * V32.y;
}
#define SHF(v, src) __shfl_sync(0xffffffffu, v, src)
#define SHF2(v, src) make_float2(SHF((v).x, src), SHF((v).y, src))
template <int MI>
__device__ __forceinline__ void kstep(float (*acck)[4], const KConst& k, int src0, float gf) {
  float2 W1[MI], W2[MI], W4[MI], W8[MI], hi[MI], G[MI], G1[MI], Wp[MI], V2[MI];
#pragma unroll
  for (int m = 0; m < MI; m++) cexp_pos(SHF(k.rl2, src0 + 4 * m), SHF(k.tr, src0 + 4 * m), gf, W1[m].x, W1[m].y);
#pragma unroll
  for (int m = 0; m < MI; m++) { W2[m] = csq(W1[m]); G[m] = cmul(SHF2(k.C, src0 + 4 * m), W1[m]); V2[m] = SHF2(k.V2, src0 + 4 * m); }
#pragma unroll
  for (int m = 0; m < MI; m++) { W4[m] = csq(W2[m]); G1[m] = cmul(G[m], V2[m]); }
#pragma unroll
  for (int m = 0; m < MI; m++) W8[m] = csq(W4[m]);
#pragma unroll
  for (int m = 0; m < MI; m++) hi[m] = cmul(W8[m], SHF2(k.V1, src0 + 4 * m));
#pragma unroll
  for (int m = 0; m < MI; m++) {
    mma_tf32(acck[0], W8[m].x, hi[m].x, W8[m].y, hi[m].y, G[m].x, -G[m].y);
    mma_tf32(acck[1], W8[m].x, hi[m].x, W8[m].y, hi[m].y, G1[m].x, -G1[m].y);
  }
#pragma unroll
  for (int m = 0; m < MI; m++) Wp[m] = csq(W8[m]);
#pragma unroll
  for (int m = 0; m < MI; m++) { hi[m] = cmul(Wp[m], V2[m]); G[m] = cmul(SHF2(k.C4, src0 + 4 * m), W2[m]); }
#pragma unroll
  for (int m = 0; m < MI; m++) mma_tf32(acck[2], Wp[m].x, hi[m].x, Wp[m].y, hi[m].y, G[m].x, -G[m].y);
#pragma unroll
  for (int m = 0; m < MI; m++) Wp[m] = csq(Wp[m]);
#pragma unroll
  for (int m = 0; m < MI; m++) { hi[m] = cmul(Wp[m], SHF2(k.V4, src0 + 4 * m)); G[m] = cmul(SHF2(k.C8, src0 + 4 * m), W4[m]); }
#pragma unroll
  for (int m = 0; m < MI; m++) mma_tf32(acck[3], Wp[m].x, hi[m].x, Wp[m].y, hi[m].y, G[m].x, -G[m].y);
#pragma unroll
  for (int m = 0; m < MI; m++) Wp[m] = csq(Wp[m]);
#pragma unroll
  for (int m = 0; m < MI; m++) { hi[m] = cmul(Wp[m], SHF2(k.V8, src0 + 4 * m)); G[m] = cmul(SHF2(k.C16, src0 + 4 * m), W8[m]); }
#pragma unroll
  for (int m = 0; m < MI; m++) mma_tf32(acck[4], Wp[m].x, hi[m].x, Wp[m].y, hi[m].y, G[m].x, -G[m].y);
}

template <int MCNT, typename F>
__device__ __forceinline__ void kgen_part(float (*acck)[4], float& k2048, const Params& p, int ch, int mbase, int lane,
                                          F&& between) {
  constexpr int NR = (MCNT + 31) / 32;
  uint32_t w[NR][2];
#pragma unroll
  for (int rd = 0; rd < NR; rd++) {
    const int n = ch * NM_ + mbase + (rd * 32 + lane < MCNT ? rd * 32 + lane : 0);
    w[rd][0] = (uint32_t)__bfloat16_as_ushort(p.lar[n]) | ((uint32_t)__bfloat16_as_ushort(p.aim[n]) << 16);
    w[rd][1] = (uint32_t)__bfloat16_as_ushort(p.cre[n]) | ((uint32_t)__bfloat16_as_ushort(p.cim[n]) << 16);
  }
  const float dt = bf16r(expf(__bfloat162float(p.logdt[ch])));
  k2048 = 0.f;
#pragma unroll
  for (int q = 0; q < 5; q++) acck[q][0] = acck[q][1] = acck[q][2] = acck[q][3] = 0.f;
#pragma unroll 1
  for (int rd = 0; rd < NR; rd++) {
    KConst kc;
    const bool valid = rd * 32 + lane < MCNT;
    uint32_t w0 = w[0][0], w1 = w[0][1];
#pragma unroll
    for (int j = 1; j < NR; j++)
      if (rd == j) { w0 = w[j][0]; w1 = w[j][1]; }
    kconst(kc, k2048, w0, w1, dt, valid);
    const int nit = min(4, (MCNT - rd * 32) >> 3);
#pragma unroll 1
    for (int it = 0; it < nit; it++) {
      kstep<2>(acck, kc, it * 8 + (lane & 3), (float)(lane >> 2));
      between();
    }
  }
#pragma unroll
  for (int o = 16; o > 0; o >>= 1) k2048 += __shfl_xor_sync(0xffffffffu, k2048, o);
}

__device__ __forceinline__ uint32_t lds32_nv(uint32_t addr) {
  uint32_t v;
  asm("ld.shared.b32 %0, [%1];" : "=r"(v) : "r"(addr));
  return v;
}
__device__ __forceinline__ void ldsm4_nv(uint32_t& r0, uint32_t& r1, uint32_t& r2, uint32_t& r3, uint32_t addr) {
  asm("ldmatrix.sync.aligned.m8n8.x4.shared.b16 {%0,%1,%2,%3}, [%4];" : "=r"(r0), "=r"(r1), "=r"(r2), "=r"(r3) : "r"(addr));
}
__device__ __forceinline__ void mma16816_nv(float* c, uint32_t a0, uint32_t a1, uint32_t a2, uint32_t a3, uint32_t b0,
                                            uint32_t b1) {
  asm("mma.sync.aligned.m16n8k16.row.col.f32.bf16.bf16.f32 {%0,%1,%2,%3},{%4,%5,%6,%7},{%8,%9},{%0,%1,%2,%3};"
      : "+f"(c[0]), "+f"(c[1]), "+f"(c[2]), "+f"(c[3])
      : "r"(a0), "r"(a1), "r"(a2), "r"(a3), "r"(b0), "r"(b1));
}
__device__ __forceinline__ void conv_main(float (*cacc)[4][4], uint32_t ptab, uint32_t ubuf, int r0, int x0, int jm, int rho) {
  uint32_t Q[2][15];
  {
    const uint32_t qb = ptab + (8 * (8 * r0 - 7) + x0 + 64) * 4;
#pragma unroll
    for (int m = 0; m < 15; m++) Q[0][m] = lds32_nv(qb + m * 32);
  }
#pragma unroll 1
  for (int r = r0; r < r0 + 4; r++) {
    uint32_t bfr[4][4][2];
#pragma unroll
    for (int q = 0; q < 4; q++)
#pragma unroll
      for (int sp = 0; sp < 2; sp++)
        ldsm4_nv(bfr[q][2 * sp][0], bfr[q][2 * sp][1], bfr[q][2 * sp + 1][0], bfr[q][2 * sp + 1][1],
                 ubuf + (8 * q + rho - r + 8) * 128 + (((4 * sp + jm) ^ ((rho - r) & 7)) << 4));
#pragma unroll
    for (int h = 0; h < 4; h++) {
      {
        const int dn = (h < 3) ? r + 8 * (h + 1) : min(r + 1, 7);
        const uint32_t qb = ptab + (8 * (8 * dn - 7) + x0 + 64) * 4;
#pragma unroll
        for (int m = 0; m < 15; m++) Q[(h + 1) & 1][m] = lds32_nv(qb + m * 32);
      }
#pragma unroll
      for (int s = 0; s < 4; s++)
#pragma unroll
        for (int i = 0; i < 4; i++) {
          const int c = 2 * (i - s) + 7;
#pragma unroll
          for (int q = h; q < 4; q++)
            mma16816_nv(cacc[i][q], Q[h & 1][c], Q[h & 1][c + 1], Q[h & 1][c - 1], Q[h & 1][c], bfr[q - h][s][0],
                        bfr[q - h][s][1]);
        }
    }
  }
}

__global__ void __cluster_dims__(2, 1, 1) __launch_bounds__(NTHREADS, 1)
    fused_kernel(const __grid_constant__ CUtensorMap tm_x, const __grid_constant__ CUtensorMap tm_wg,
                 const __grid_constant__ CUtensorMap tm_wu, const __grid_constant__ CUtensorMap tm_h,
                 const __grid_constant__ CUtensorMap tm_wd, const __grid_constant__ CUtensorMap tm_yT,
                 const __grid_constant__ CUtensorMap tm_xnT, const __grid_constant__ CUtensorMap tm_u, const Params p) {
  extern __shared__ uint8_t smem_raw[];
  const uint32_t sbase = (smem_u32(smem_raw) + 1023u) & ~1023u;
  const int warp = threadIdx.x >> 5, lane = threadIdx.x & 31;
  const int bid = blockIdx.x;
  const int rank = bid & 1, cl = bid >> 1;
  const int sA = cl & 7, mA = 2 * (cl >> 3) + rank;
  const int mC = cl >> 2, jC = 2 * (cl & 3) + rank;
  const uint32_t bars = sbase + OFF_BAR;

  if (lane == 0 && warp >= 8) {
    const int base = warp == 12 ? 0 : (warp < 12 ? warp - 7 : warp - 8) * 13;
#pragma unroll
    for (int j = 0; j < 13; j++) {
      const int i = base + j;
      uint32_t cnt = 1;
      if (i >= B_EMPTY && i < B_EMPTY + 13) cnt = 16;
      else if ((i >= B_EMPTY2 && i < B_EMPTY2 + NST2) || i == B_CONV) cnt = 16;
      else if (i == B_UF) cnt = 4;
      else if (i == B_H) cnt = 12;
      else if (i == B_KGEN) cnt = 5;
      else if (i == B_XN || i == B_KD || i == B_Y || i == B_H2) cnt = 8;
      mbar_init(bars + i * 8, cnt);
    }
    asm volatile("fence.mbarrier_init.release.cluster;" ::: "memory");
    if (warp == 12) {
      for (int kb = 0; kb < 8; kb++) {
        const int slot = kb < 4 ? 9 + kb : kb - 4;
        mbar_expect_tx(bars + (B_FULL + slot) * 8, SLOT);
        tma_load(sbase + slot * SLOT, &tm_x, bars + (B_FULL + slot) * 8, kb * 64, mA * 128);
      }
    }
  }
  __syncwarp();
  asm volatile("barrier.cluster.arrive.relaxed.aligned;" ::: "memory");
  TS(1);

  if (warp < 8) {
    const int g = lane >> 2, t4 = lane & 3;
    const int wq = warp & 3, wg = warp >> 2;
    const uint32_t stg = sbase + OFF_STAGE + warp * 2048;
    {
      float acck[5][4];
      float k2048;
      kgen_part<64>(acck, k2048, p, bid * 4 + (warp >> 1), (warp & 1) * 64, lane, []() {});
      asm volatile("setmaxnreg.inc.sync.aligned.u32 224;");
      asm volatile("barrier.cluster.wait.acquire.aligned;" ::: "memory");
      uint32_t afr[32][4];
      float inv0, inv1;
      {
        const int jm = lane >> 3, rho = lane & 7;
        const int row = warp * 16 + (jm & 1) * 8 + rho;
#pragma unroll
        for (int kb = 0; kb < 8; kb++) {
          const int slot = kb < 4 ? 9 + kb : kb - 4;
          mbar_wait(bars + (B_FULL + slot) * 8, 0);
          const uint32_t sb = sbase + slot * SLOT + row * 128;
#pragma unroll
          for (int k = 0; k < 4; k++) {
            int chunk = 2 * k + (jm >> 1);
            ldsm4(afr[kb * 4 + k][0], afr[kb * 4 + k][1], afr[kb * 4 + k][2], afr[kb * 4 + k][3],
                  sb + ((chunk ^ (row & 7)) << 4));
          }
          __syncwarp();
          if (lane == 0) {
            mbar_arrive_cluster(bars + (B_EMPTY + slot) * 8, 0);
            mbar_arrive_cluster(bars + (B_EMPTY + slot) * 8, 1);
          }
        }
      }
      {
#pragma unroll
        for (int i = 9; i < 13; i++) mbar_wait(bars + (B_EMPTY + i) * 8, 0);
        const uint32_t kd = sbase + OFF_UBUF + (warp >> 1) * UBUF_BYTES + (warp & 1) * 2576;
#pragma unroll
        for (int q = 0; q < 5; q++)
#pragma unroll
          for (int e = 0; e < 4; e += 2)
            asm volatile("st.shared.v2.f32 [%0], {%1,%2};" ::"r"(kd + (128 * q + 2 * t4 + 8 * (g + (e >> 1) * 8)) * 4),
                         "f"(acck[q][e]), "f"(acck[q][e + 1]) : "memory");
        if (lane == 0) sts32(kd + 640 * 4, __float_as_uint(k2048));
        __syncwarp();
        if (lane == 0) mbar_arrive(bars + B_KD * 8);
      }
      TS(2);
      {
        float c0[4] = {0.f, 0.f, 0.f, 0.f}, c1[4] = {0.f, 0.f, 0.f, 0.f};
        float c2[4] = {0.f, 0.f, 0.f, 0.f}, c3[4] = {0.f, 0.f, 0.f, 0.f};
        float c4[4] = {0.f, 0.f, 0.f, 0.f}, c5[4] = {0.f, 0.f, 0.f, 0.f};
        float c6[4] = {0.f, 0.f, 0.f, 0.f}, c7[4] = {0.f, 0.f, 0.f, 0.f};
        const uint32_t ONE = 0x3f803f80u;
#pragma unroll
        for (int ks = 0; ks < 32; ks += 4) {
          mma16816(c0, afr[ks][0], ONE, afr[ks][2], ONE, afr[ks][0], afr[ks][2]);
          mma16816(c1, afr[ks][1], ONE, afr[ks][3], ONE, afr[ks][1], afr[ks][3]);
          mma16816(c2, afr[ks + 1][0], ONE, afr[ks + 1][2], ONE, afr[ks + 1][0], afr[ks + 1][2]);
          mma16816(c3, afr[ks + 1][1], ONE, afr[ks + 1][3], ONE, afr[ks + 1][1], afr[ks + 1][3]);
          mma16816(c4, afr[ks + 2][0], ONE, afr[ks + 2][2], ONE, afr[ks + 2][0], afr[ks + 2][2]);
          mma16816(c5, afr[ks + 2][1], ONE, afr[ks + 2][3], ONE, afr[ks + 2][1], afr[ks + 2][3]);
          mma16816(c6, afr[ks + 3][0], ONE, afr[ks + 3][2], ONE, afr[ks + 3][0], afr[ks + 3][2]);
          mma16816(c7, afr[ks + 3][1], ONE, afr[ks + 3][3], ONE, afr[ks + 3][1], afr[ks + 3][3]);
        }
#pragma unroll
        for (int e = 0; e < 4; e++) {
          c0[e] = (c0[e] + c2[e]) + (c4[e] + c6[e]);
          c1[e] = (c1[e] + c3[e]) + (c5[e] + c7[e]);
        }
        const int src = 4 * g + (g >> 1);
        float sq0 = __shfl_sync(0xffffffffu, (g & 1) ? c0[1] : c0[0], src);
        float sm0 = __shfl_sync(0xffffffffu, (g & 1) ? c0[3] : c0[2], src);
        float sq1 = __shfl_sync(0xffffffffu, (g & 1) ? c1[1] : c1[0], src);
        float sm1 = __shfl_sync(0xffffffffu, (g & 1) ? c1[3] : c1[2], src);
        float mean0 = sm0 * (1.f / D_), mean1 = sm1 * (1.f / D_);
        float var0 = sq0 * (1.f / D_) - mean0 * mean0, var1 = sq1 * (1.f / D_) - mean1 * mean1;
        bool bad = !(mean0 * mean0 <= 16.f * var0) || !(mean1 * mean1 <= 16.f * var1);
        if (__any_sync(0xffffffffu, bad)) {
          float a0 = 0.f, a1 = 0.f;
#pragma unroll
          for (int ks = 0; ks < 32; ks++) {
            float d;
            d = bf_lo(afr[ks][0]) - mean0; a0 += d * d;
            d = bf_hi(afr[ks][0]) - mean0; a0 += d * d;
            d = bf_lo(afr[ks][2]) - mean0; a0 += d * d;
            d = bf_hi(afr[ks][2]) - mean0; a0 += d * d;
            d = bf_lo(afr[ks][1]) - mean1; a1 += d * d;
            d = bf_hi(afr[ks][1]) - mean1; a1 += d * d;
            d = bf_lo(afr[ks][3]) - mean1; a1 += d * d;
            d = bf_hi(afr[ks][3]) - mean1; a1 += d * d;
          }
          a0 += __shfl_xor_sync(0xffffffffu, a0, 1);
          a0 += __shfl_xor_sync(0xffffffffu, a0, 2);
          a1 += __shfl_xor_sync(0xffffffffu, a1, 1);
          a1 += __shfl_xor_sync(0xffffffffu, a1, 2);
          var0 = a0 * (1.f / D_);
          var1 = a1 * (1.f / D_);
        }
        float den0 = bf16r(sqrtf(bf16r(bf16r(var0) + 1e-5f)));
        float den1 = bf16r(sqrtf(bf16r(bf16r(var1) + 1e-5f)));
        inv0 = 1.f / den0;
        inv1 = 1.f / den1;
        const uint32_t m0 = pack_bf16(mean0, mean0), m1 = pack_bf16(mean1, mean1);
#pragma unroll
        for (int ks = 0; ks < 32; ks++) {
#pragma unroll
          for (int r = 0; r < 4; r++) afr[ks][r] = hsub2_bf(afr[ks][r], (r & 1) ? m1 : m0);
        }
      }
      TS(3);
      {
        const int jm = lane >> 3, rho = lane & 7;
        uint32_t xs[4][4];
#pragma unroll
        for (int kb = 0; kb < 8; kb++) {
          if (kb == sA) {
#pragma unroll
            for (int k = 0; k < 4; k++)
#pragma unroll
              for (int r = 0; r < 4; r++) xs[k][r] = afr[kb * 4 + k][r];
          }
        }
#pragma unroll
        for (int k = 0; k < 4; k++) {
#pragma unroll
          for (int r = 0; r < 4; r++) {
            const float iv = (r & 1) ? inv1 : inv0;
            xs[k][r] = pack_bf16(bf_lo(xs[k][r]) * iv, bf_hi(xs[k][r]) * iv);
          }
          int c = k * 16 + (jm >> 1) * 8 + rho;
          stsm4t(stg + c * 32 + (jm & 1) * 16, xs[k][0], xs[k][1], xs[k][2], xs[k][3]);
        }
        __syncwarp();
#pragma unroll
        for (int it = 0; it < 4; it++) {
          int idx = it * 32 + lane;
          int c = idx >> 1, hf = idx & 1;
          uint4 v = lds128(stg + c * 32 + hf * 16);
          stg128(g_xnT + (size_t)(sA * 64 + c) * L_ + mA * 128 + warp * 16 + hf * 8, v);
        }
        __syncwarp();
        if (lane == 0) mbar_arrive(bars + B_XN * 8);
      }
      TS(4);
      {
        float acc[64];
        int slot = 4, ph = 0, prev = 0;
        const uint64_t dbase = mkdesc(sbase + OFF_RING, 8192, 512, 2);
        const int jm = lane >> 3, rho = lane & 7;
        const int srow = (jm & 1) * 8 + rho;
        auto handoff = [&](const float* a, int u) {
          mbar_wait(bars + (B_HE + (u & 1) * 8 + warp) * 8, ((u >> 1) & 1) ^ 1);
          const uint32_t sg = sbase + ((u & 1) ? 8 * SLOT : OFF_STAGE) + warp * 2048;
#pragma unroll
          for (int j = 0; j < 8; j += 2) {
            const int chunk = j + (jm >> 1);
            stsm4(sg + srow * 128 + ((chunk ^ (srow & 7)) << 4), pack_bf16(a[4 * j] * inv0, a[4 * j + 1] * inv0),
                  pack_bf16(a[4 * j + 2] * inv1, a[4 * j + 3] * inv1), pack_bf16(a[4 * j + 4] * inv0, a[4 * j + 5] * inv0),
                  pack_bf16(a[4 * j + 6] * inv1, a[4 * j + 7] * inv1));
          }
          __syncwarp();
          if (lane == 0) mbar_arrive(bars + (B_HF + (u & 1) * 8 + warp) * 8);
        };
        auto release = [&](int sl) {
          if (lane == 0) {
            mbar_arrive_cluster(bars + (B_EMPTY + sl) * 8, 0);
            mbar_arrive_cluster(bars + (B_EMPTY + sl) * 8, 1);
          }
        };
        if (wg == 1) named_bar_sync(8, 256);
#pragma unroll 1
        for (int U = 0; U < 3; U++) {
#pragma unroll
          for (int sb = 0; sb < 4; sb++) {
            if (sb == 1 && U == 0 && wg == 0) asm volatile("bar.arrive 8, 256;" ::: "memory");
            mbar_wait(bars + (B_FULL + slot) * 8, ph);
            mbar_wait(bars + (B_FULL + slot + 1) * 8, ph);
            const uint64_t db = dbase + (uint64_t)(slot * (SLOT >> 4));
            wg_fence();
#pragma unroll
            for (int k = 0; k < 8; k++) wg_rs_n128(acc, afr[sb * 8 + k], db + k * 64, (sb | k) != 0);
            wg_commit();
            if (sb > 0) {
              wg_wait<1>();
              release(prev);
              release(prev + 1);
            }
            prev = slot;
            slot += 2;
            if (slot == 8) { slot = 0; ph ^= 1; }
          }
          wg_wait<0>();
          release(prev);
          release(prev + 1);
          handoff(acc, 2 * U);
          handoff(acc + 32, 2 * U + 1);
        }
#pragma unroll
        for (int sb = 0; sb < 4; sb++) {
          mbar_wait(bars + (B_FULL + slot) * 8, ph);
          const uint64_t db = dbase + (uint64_t)(slot * (SLOT >> 4));
          wg_fence();
#pragma unroll
          for (int k = 0; k < 8; k++) wg_rs_n64(acc, afr[sb * 8 + k], db + k * 64, (sb | k) != 0);
          wg_commit();
          if (sb > 0) {
            wg_wait<1>();
            release(prev);
          }
          prev = slot;
          if (++slot == 8) { slot = 0; ph ^= 1; }
        }
        wg_wait<0>();
        release(prev);
        {
          uint32_t gp[8], up[8];
#pragma unroll
          for (int j = 0; j < 8; j++) {
            const float iv = (j & 1) ? inv1 : inv0;
            gp[j] = pack_bf16(acc[2 * j] * iv, acc[2 * j + 1] * iv);
            up[j] = pack_bf16(acc[16 + 2 * j] * iv, acc[16 + 2 * j + 1] * iv);
          }
          mbar_wait(bars + (B_HE + warp) * 8, 0);
          unit_epilogue(gp, up, stg, g_h + (size_t)(mA * 128 + warp * 16) * F_ + sA * 224 + 192, lane);
          if (lane == 0) mbar_arrive(bars + B_H * 8);
        }
      }
    }
    TS(5);
    {
      const int cs = warp >> 1, hf = warp & 1;
      uint32_t ptab = sbase + OFF_PTAB + cs * PTAB_BYTES;
      uint32_t ubuf = sbase + OFF_UBUF + cs * UBUF_BYTES;
      mbar_wait(bars + B_KGEN * 8, 0);
      asm volatile("" : "+r"(ptab), "+r"(ubuf)::"memory");
      TS(6);
      const int jm = lane >> 3, rho = lane & 7;
      float cacc[4][4][4];
#pragma unroll
      for (int i = 0; i < 4; i++)
#pragma unroll
        for (int q = 0; q < 4; q++) cacc[i][q][0] = cacc[i][q][1] = cacc[i][q][2] = cacc[i][q][3] = 0.f;
      conv_main(cacc, ptab, ubuf, 4 * hf, g - 2 * t4, jm, rho);
      TS(7);
      named_bar_sync(1 + cs, 64);
      const uint32_t xw = ptab + hf * 4096, xr = ptab + (hf ^ 1) * 4096;
#pragma unroll
      for (int i = 0; i < 4; i++)
#pragma unroll
        for (int qq = 0; qq < 2; qq++) {
          uint4 v;
          v.x = __float_as_uint(hf ? cacc[i][qq][0] : cacc[i][2 + qq][0]);
          v.y = __float_as_uint(hf ? cacc[i][qq][1] : cacc[i][2 + qq][1]);
          v.z = __float_as_uint(hf ? cacc[i][qq][2] : cacc[i][2 + qq][2]);
          v.w = __float_as_uint(hf ? cacc[i][qq][3] : cacc[i][2 + qq][3]);
          sts128(xw + ((i * 2 + qq) * 32 + lane) * 16, v);
        }
      named_bar_sync(1 + cs, 64);
      const uint32_t yb = ubuf + hf * 2304;
#pragma unroll
      for (int i = 0; i < 4; i++) {
        uint32_t pk[4];
#pragma unroll
        for (int qq = 0; qq < 2; qq++) {
          const uint4 v = lds128(xr + ((i * 2 + qq) * 32 + lane) * 16);
          const float y0 = (hf ? cacc[i][2 + qq][0] : cacc[i][qq][0]) + __uint_as_float(v.x);
          const float y1 = (hf ? cacc[i][2 + qq][1] : cacc[i][qq][1]) + __uint_as_float(v.y);
          const float y2 = (hf ? cacc[i][2 + qq][2] : cacc[i][qq][2]) + __uint_as_float(v.z);
          const float y3 = (hf ? cacc[i][2 + qq][3] : cacc[i][qq][3]) + __uint_as_float(v.w);
          pk[2 * qq] = pack_bf16(y0, y1);
          pk[2 * qq + 1] = pack_bf16(y2, y3);
        }
        stsm4t(yb + (8 * (jm >> 1) + rho) * 144 + (16 * i + (jm & 1) * 8) * 2, pk[0], pk[1], pk[2], pk[3]);
      }
      __syncwarp();
      bf16* dst = g_yT + (size_t)(bid * 4 + cs) * L_ + hf * 1024;
#pragma unroll
      for (int it = 0; it < 4; it++) {
        int idx = it * 32 + lane;
        stg128(dst + idx * 8, lds128(yb + (idx >> 3) * 144 + (idx & 7) * 16));
      }
      asm volatile("fence.proxy.async.shared::cta;" ::: "memory");
      __syncwarp();
      if (lane == 0) {
        mbar_arrive(bars + B_Y * 8);
        mbar_arrive_cluster(bars + B_CONV * 8, 0);
        mbar_arrive_cluster(bars + B_CONV * 8, 1);
      }
    }
    TS(8);
    {
      float acc[32];
      int st = 0, ph = 0;
      const uint64_t da0 = mkdesc(sbase + OFF_RING + wg * 8192, 16, 1024), db0 = mkdesc(sbase + OFF_RING + 16384, 8192, 1024);
#pragma unroll 1
      for (int kb = 0; kb < 28; kb++) {
        mbar_wait(bars + (B_FULL2 + st) * 8, ph);
        const uint64_t da = da0 + (uint64_t)(st * (CST >> 4)), db = db0 + (uint64_t)(st * (CST >> 4));
        wg_fence();
#pragma unroll
        for (int k = 0; k < 4; k++) wg_ss_n64(acc, da + k * 2, db + k * 128, (kb | k) != 0);
        wg_commit();
        wg_wait<0>();
        if (lane == 0) {
          mbar_arrive_cluster(bars + (B_EMPTY2 + st) * 8, 0);
          mbar_arrive_cluster(bars + (B_EMPTY2 + st) * 8, 1);
        }
        if (++st == NST2) { st = 0; ph ^= 1; }
      }
      TS(9);
      const int jm = lane >> 3, rho = lane & 7;
      uint32_t dsk[8];
#pragma unroll
      for (int j = 0; j < 8; j++) dsk[j] = *reinterpret_cast<const uint32_t*>(p.dskip + jC * 64 + 8 * j + 2 * t4);
      mbar_wait(bars + (B_FULL2 + 4) * 8, 1);
      mbar_wait(bars + (B_FULL2 + 5) * 8, 1);
      TS(10);
      const uint32_t xt = sbase + OFF_RING + 4 * CST, yt = sbase + OFF_RING + 4 * CST + 16384 + wg * 8192,
                     nt = sbase + OFF_RING + 5 * CST + 8192 + wg * 8192;
      const int srow = (jm & 1) * 8 + rho;
#pragma unroll
      for (int j = 0; j < 8; j += 2) {
        uint32_t xv[4], yv[4], nv[4], ov[4];
        {
          int row = warp * 16 + srow, chunk = j + (jm >> 1);
          ldsm4(xv[0], xv[1], xv[2], xv[3], xt + row * 128 + ((chunk ^ (row & 7)) << 4));
        }
        {
          int c = 8 * (j + (jm >> 1)) + rho, tch = 2 * wq + (jm & 1);
          uint32_t off = c * 128 + ((tch ^ (c & 7)) << 4);
          ldsm4t(yv[0], yv[1], yv[2], yv[3], yt + off);
          ldsm4t(nv[0], nv[1], nv[2], nv[3], nt + off);
        }
#pragma unroll
        for (int e = 0; e < 4; e++) {
          uint32_t t3 = hadd2_bf(xv[e], hadd2_bf(yv[e], hmul2_bf(nv[e], dsk[j + (e >> 1)])));
          ov[e] = hadd2_bf(t3, pack_bf16(acc[4 * j + 2 * e], acc[4 * j + 2 * e + 1]));
        }
        const int chunk = j + (jm >> 1);
        stsm4(stg + srow * 128 + ((chunk ^ (srow & 7)) << 4), ov[0], ov[1], ov[2], ov[3]);
      }
      __syncwarp();
      bf16* optr = p.out + (size_t)(mC * 128 + warp * 16) * D_ + jC * 64;
#pragma unroll
      for (int it = 0; it < 4; it++) {
        int r = it * 4 + (lane >> 3), c = lane & 7;
        stg128(optr + (size_t)r * D_ + c * 8, lds128(stg + r * 128 + ((c ^ (r & 7)) << 4)));
      }
    }
    TS(11);
    cluster_sync_all();
    TS(12);
  } else if (warp < 12) {
    asm volatile("setmaxnreg.dec.sync.aligned.u32 40;");
    asm volatile("barrier.cluster.wait.acquire.aligned;" ::: "memory");
    const int cs = warp - 8;
    const int ch = bid * 4 + cs;
    const int g = lane >> 2, t4 = lane & 3;
    const uint32_t kd = sbase + OFF_UBUF + cs * UBUF_BYTES;
    const uint32_t ptab = sbase + OFF_PTAB + cs * PTAB_BYTES;
    const uint32_t kdb = sbase + OFF_KDB + cs * 1312;
    int git = 0;
    auto geglu = [&]() {
      const int row = lane >> 1, hf = lane & 1;
      const int u = git < 12 ? (git >> 2) * 2 + (git & 1) : 6, cw = 2 * cs + (git < 12 ? (git >> 1) & 1 : git & 1);
      const uint32_t sb = sbase + ((u & 1) ? 8 * SLOT : OFF_STAGE) + cw * 2048 + row * 128;
      uint4 gv[2], uv[2];
#pragma unroll
      for (int c = 0; c < 2; c++) {
        gv[c] = lds128(sb + (((2 * hf + c) ^ (row & 7)) << 4));
        uv[c] = lds128(sb + (((4 + 2 * hf + c) ^ (row & 7)) << 4));
      }
      __syncwarp();
      if (lane == 0) mbar_arrive(bars + (B_HE + (u & 1) * 8 + cw) * 8);
      bf16* hp = g_h + (size_t)(mA * 128 + cw * 16 + row) * F_ + sA * 224 + u * 32 + hf * 16;
#pragma unroll
      for (int c = 0; c < 2; c++) {
        uint4 o;
        o.x = hmul2_bf(pack_bf16(gelu_tanh(bf_lo(gv[c].x)), gelu_tanh(bf_hi(gv[c].x))), uv[c].x);
        o.y = hmul2_bf(pack_bf16(gelu_tanh(bf_lo(gv[c].y)), gelu_tanh(bf_hi(gv[c].y))), uv[c].y);
        o.z = hmul2_bf(pack_bf16(gelu_tanh(bf_lo(gv[c].z)), gelu_tanh(bf_hi(gv[c].z))), uv[c].z);
        o.w = hmul2_bf(pack_bf16(gelu_tanh(bf_lo(gv[c].w)), gelu_tanh(bf_hi(gv[c].w))), uv[c].w);
        stg128(hp + c * 8, o);
      }
      git++;
    };
    auto hf_bar = [&]() {
      const int u = git < 12 ? (git >> 2) * 2 + (git & 1) : 6, cw = 2 * cs + (git < 12 ? (git >> 1) & 1 : git & 1);
      return bars + (B_HF + (u & 1) * 8 + cw) * 8;
    };
    auto hf_par = [&]() { return (uint32_t)((git >> 2) & 1); };
    auto poll_geglu = [&]() {
      while (git < 12 && mbar_test(hf_bar(), hf_par())) geglu();
    };
    {
      mbar_wait_sleep(bars + B_KD * 8, 0);
      TS(2);
#pragma unroll
      for (int q = 0; q < 5; q++)
#pragma unroll
        for (int e = 0; e < 4; e += 2) {
          const uint32_t ad = kd + (128 * q + 2 * t4 + 8 * (g + (e >> 1) * 8)) * 4;
          float a0, a1, b0, b1;
          asm volatile("ld.shared.v2.f32 {%0,%1}, [%2];" : "=f"(a0), "=f"(a1) : "r"(ad) : "memory");
          asm volatile("ld.shared.v2.f32 {%0,%1}, [%2];" : "=f"(b0), "=f"(b1) : "r"(ad + 2576) : "memory");
          sts32(kdb + (128 * q + 2 * t4 + 8 * (g + (e >> 1) * 8)) * 2, pack_bf16(a0 + b0, a1 + b1));
        }
      if (lane == 0)
        sts32(kdb + 640 * 2, pack_bf16(__uint_as_float(lds32(kd + 640 * 4)) + __uint_as_float(lds32(kd + 2576 + 640 * 4)), 0.f));
      sts32(ptab + lane * 4, 0u);
      sts32(ptab + (32 + lane) * 4, 0u);
      __syncwarp();
      sts128(kd + lane * 16, make_uint4(0, 0, 0, 0));
      sts128(kd + 512 + lane * 16, make_uint4(0, 0, 0, 0));
      asm volatile("fence.proxy.async.shared::cta;" ::: "memory");
      __syncwarp();
      if (lane == 0) mbar_arrive(bars + B_UF * 8);
      TS(4);
    }
#pragma unroll 1
    for (int base = 0; base < 2048; base += 256) {
      uint32_t kv[2][5];
#pragma unroll
      for (int j = 0; j < 2; j++)
#pragma unroll
        for (int e = 0; e < 5; e++) {
          const int x = base + j * 128 + lane * 4 + e - 1;
          uint16_t v;
          asm volatile("ld.shared.u16 %0, [%1];" : "=h"(v) : "r"(kdb + kidx(max(x, 0)) * 2) : "memory");
          kv[j][e] = x < 0 ? 0u : (uint32_t)v;
        }
#pragma unroll
      for (int j = 0; j < 2; j++)
        sts128(ptab + (base + j * 128 + lane * 4 + 64) * 4,
               make_uint4(kv[j][1] | (kv[j][0] << 16), kv[j][2] | (kv[j][1] << 16), kv[j][3] | (kv[j][2] << 16),
                          kv[j][4] | (kv[j][3] << 16)));
    }
    __syncwarp();
    if (lane == 0) mbar_arrive(bars + B_KGEN * 8);
    TS(3);
    {
#pragma unroll 1
      while (git < 12) {
        mbar_wait(hf_bar(), hf_par());
        geglu();
      }
      __syncwarp();
      asm volatile("fence.proxy.async.shared::cta;" ::: "memory");
      __syncwarp();
      if (lane == 0) {
        mbar_arrive(bars + B_H * 8);
        mbar_arrive_cluster(bars + B_H2 * 8, 0);
        mbar_arrive_cluster(bars + B_H2 * 8, 1);
      }
    }
    cluster_sync_all();
  } else {
    asm volatile("setmaxnreg.dec.sync.aligned.u32 24;");
    asm volatile("barrier.cluster.wait.acquire.aligned;" ::: "memory");
    TS(3);
    if (threadIdx.x == 384) {
      int slot = 4, ph = 0;
      const CUtensorMap* tw = rank == 0 ? &tm_wg : &tm_wu;
      for (int n = 0; n < 28; n++) {
        const int u = n < 24 ? (n >> 3) * 2 + (n & 1) : 6, sb = n < 24 ? (n >> 1) & 3 : n - 24;
        if (n == 16) {
          mbar_wait(bars + B_UF * 8, 0);
          poll_ge(&g_cnt[0], NCTA);
          fence_proxy_async();
          mbar_expect_tx(bars + B_KGEN * 8, 16384);
          for (int c = 0; c < 4; c++)
            tma_load(sbase + OFF_UBUF + c * UBUF_BYTES + 1024, &tm_u, bars + B_KGEN * 8, 0, (bid * 4 + c) * 32);
        }
        mbar_wait(bars + (B_EMPTY + slot) * 8, ph ^ 1);
        mbar_expect_tx(bars + (B_FULL + slot) * 8, SLOT);
        tma_load_mc(sbase + OFF_RING + slot * SLOT + rank * 8192, tw, bars + (B_FULL + slot) * 8, sA * 224 + u * 32,
                    sb * 128);
        if (++slot == 8) { slot = 0; ph ^= 1; }
      }
      for (int i = 0; i < 8; i++) {
        mbar_wait(bars + (B_EMPTY + slot) * 8, ph ^ 1);
        if (++slot == 8) { slot = 0; ph ^= 1; }
      }
      mbar_wait(bars + B_H2 * 8, 0);
      for (int st = 0; st < 6; st++) {
        mbar_expect_tx(bars + (B_FULL2 + st) * 8, CST);
        tma_load(sbase + OFF_RING + st * CST + 16384, &tm_wd, bars + (B_FULL2 + st) * 8, jC * 64, st * 64);
      }
      poll_ge(&g_cnt[8 + mC], 8);
      fence_proxy_async();
      for (int st = 0; st < 6; st++)
        tma_load_mc(sbase + OFF_RING + st * CST + rank * 8192, &tm_h, bars + (B_FULL2 + st) * 8, st * 64,
                    mC * 128 + rank * 64);
      poll_ge(&g_cnt[0], NCTA);
      fence_proxy_async();
      mbar_wait(bars + B_CONV * 8, 0);
      int st = 6, ph2 = 1;
      for (int kb = 6; kb < 28; kb++) {
        mbar_wait(bars + (B_EMPTY2 + st) * 8, ph2);
        mbar_expect_tx(bars + (B_FULL2 + st) * 8, CST);
        tma_load(sbase + OFF_RING + st * CST + 16384, &tm_wd, bars + (B_FULL2 + st) * 8, jC * 64, kb * 64);
        tma_load_mc(sbase + OFF_RING + st * CST + rank * 8192, &tm_h, bars + (B_FULL2 + st) * 8, kb * 64,
                    mC * 128 + rank * 64);
        if (++st == NST2) { st = 0; ph2 ^= 1; }
      }
      mbar_wait(bars + (B_EMPTY2 + 4) * 8, 0);
      mbar_expect_tx(bars + (B_FULL2 + 4) * 8, CST);
      tma_load(sbase + OFF_RING + 4 * CST, &tm_x, bars + (B_FULL2 + 4) * 8, jC * 64, mC * 128);
      mbar_wait(bars + (B_EMPTY2 + 5) * 8, 0);
      mbar_expect_tx(bars + (B_FULL2 + 5) * 8, CST);
      for (int w = 0; w < 2; w++)
        tma_load(sbase + OFF_RING + 5 * CST + 8192 + w * 8192, &tm_xnT, bars + (B_FULL2 + 5) * 8, mC * 128 + w * 64, jC * 64);
      poll_ge(&g_cnt[24 + jC], 16);
      fence_proxy_async();
      tma_load(sbase + OFF_RING + 4 * CST + 16384, &tm_yT, bars + (B_FULL2 + 4) * 8, mC * 128, jC * 64);
      tma_load(sbase + OFF_RING + 5 * CST, &tm_yT, bars + (B_FULL2 + 5) * 8, mC * 128 + 64, jC * 64);
    }
    else if (lane == 0) {
      mbar_wait_sleep(bars + (B_XN + warp - 13) * 8, 0);
      red_release(warp == 13 ? &g_cnt[0] : (warp == 14 ? &g_cnt[8 + mA] : &g_cnt[24 + (bid >> 4)]));
    }
    __syncwarp();
    cluster_sync_all();
    if (threadIdx.x == 384) {
      unsigned int old = atomicAdd(&g_cnt[1], 1u);
      if (old == NCTA - 1) {
        for (int i = 0; i < 32; i++) g_cnt[i] = 0;
        __threadfence();
      }
    }
  }
}

typedef CUresult (*EncFn)(CUtensorMap*, CUtensorMapDataType, cuuint32_t, void*, const cuuint64_t*, const cuuint64_t*,
                          const cuuint32_t*, const cuuint32_t*, CUtensorMapInterleave, CUtensorMapSwizzle,
                          CUtensorMapL2promotion, CUtensorMapFloatOOBfill);

void make_map(EncFn enc, CUtensorMap* tm, const void* ptr, uint64_t cols, uint64_t rows, uint32_t bcols, uint32_t brows,
              CUtensorMapSwizzle swz = CU_TENSOR_MAP_SWIZZLE_128B) {
  cuuint64_t gd[2] = {cols, rows};
  cuuint64_t gs[1] = {cols * 2};
  cuuint32_t bd[2] = {bcols, brows};
  cuuint32_t es[2] = {1, 1};
  enc(tm, CU_TENSOR_MAP_DATA_TYPE_BFLOAT16, 2, const_cast<void*>(ptr), gd, gs, bd, es, CU_TENSOR_MAP_INTERLEAVE_NONE,
      swz, CU_TENSOR_MAP_L2_PROMOTION_L2_128B, CU_TENSOR_MAP_FLOAT_OOB_FILL_NONE);
}

}

extern "C" void kernel_launch(void* const* d_in, const int* in_sizes, int n_in, void* d_out, int out_size) {
  static EncFn enc = nullptr;
  static void *p_xnT = nullptr, *p_yT = nullptr, *p_h = nullptr;
  if (!enc) {
    void* fn = nullptr;
    cudaDriverEntryPointQueryResult qr;
    cudaGetDriverEntryPoint("cuTensorMapEncodeTiled", &fn, cudaEnableDefault, &qr);
    enc = (EncFn)fn;
    cudaGetSymbolAddress(&p_xnT, g_xnT);
    cudaGetSymbolAddress(&p_yT, g_yT);
    cudaGetSymbolAddress(&p_h, g_h);
    cudaFuncSetAttribute(fused_kernel, cudaFuncAttributeMaxDynamicSharedMemorySize, SMEM_BYTES);
  }
  CUtensorMap tm_x, tm_wg, tm_wu, tm_h, tm_wd, tm_yT, tm_xnT, tm_u;
  make_map(enc, &tm_x, d_in[0], D_, L_, 64, 128);
  make_map(enc, &tm_wg, d_in[8], F_, D_, 32, 128, CU_TENSOR_MAP_SWIZZLE_64B);
  make_map(enc, &tm_wu, d_in[9], F_, D_, 32, 128, CU_TENSOR_MAP_SWIZZLE_64B);
  make_map(enc, &tm_h, p_h, F_, L_, 64, 64);
  make_map(enc, &tm_wd, d_in[10], D_, F_, 64, 64);
  make_map(enc, &tm_yT, p_yT, L_, D_, 64, 64);
  make_map(enc, &tm_xnT, p_xnT, L_, D_, 64, 64);
  make_map(enc, &tm_u, p_xnT, 64, D_ * 32, 64, 32);
  Params p;
  p.lar = (const bf16*)d_in[1];
  p.aim = (const bf16*)d_in[2];
  p.cre = (const bf16*)d_in[3];
  p.cim = (const bf16*)d_in[4];
  p.logdt = (const bf16*)d_in[5];
  p.dskip = (const bf16*)d_in[6];
  p.out = (bf16*)d_out;
  fused_kernel<<<NCTA, NTHREADS, SMEM_BYTES>>>(tm_x, tm_wg, tm_wu, tm_h, tm_wd, tm_yT, tm_xnT, tm_u, p);
}
```
